```python
import torch

def _softmax(x, axis=-1):
    return torch.softmax(x, dim=axis)
def _gelu(x):
    return torch.nn.functional.gelu(x, approximate="tanh")
def _silu(x):
    return torch.nn.functional.silu(x)
def _sigmoid(x):
    return torch.sigmoid(x)
def _layernorm(x, axis=-1, eps=1e-5):
    m = x.mean(dim=axis, keepdim=True)
    v = x.var(dim=axis, keepdim=True, unbiased=False)
    return (x - m) / torch.sqrt(v + eps)
def _scatter_add(tgt, idx, src, axis=0):
    return tgt.clone().index_add_(axis, idx, src)
def _segment_sum(src, seg, n):
    out = torch.zeros((n,) + src.shape[1:], dtype=src.dtype)
    return out.index_add_(0, seg, src)
def _pad(x, pw):
    flat = tuple(v for pair in reversed(pw) for v in pair)
    return torch.nn.functional.pad(x, flat)

kernel_name = 'gated_mix__ssm_conv_h3__sliding_block__prompt'

def setup_inputs():

    _w = (lambda a: (lambda t: t.to(torch.bfloat16) if t.is_floating_point() else t)(torch.as_tensor(a)))
    def _A_setup():
        B, S, D = 1, 2048, 576
        ks = 4
        return {
            "q": _w((lambda *s: torch.randn(*s, dtype=torch.bfloat16) * 0.05)(B, S, D)),
            "k": _w((lambda *s: torch.randn(*s, dtype=torch.bfloat16) * 0.8)(B, S, D)),
            "v": _w((lambda *s: torch.randn(*s, dtype=torch.bfloat16) * 0.8)(B, S, D)),
            "shift_k": _w((lambda *s: torch.randn(*s, dtype=torch.bfloat16) * 0.8)(D, ks) * 0.5),
            "ssm_k": _w((lambda *s: torch.randn(*s, dtype=torch.bfloat16) * 3.2)(D, S) * (1.0 / S ** 0.5)),
            "ssm_D": _w((lambda *s: torch.randn(*s, dtype=torch.bfloat16) * 0.8)(D)),
        }
    _A_in = _A_setup()

    def _B_setup():
        B, S, D = 1, 2048, 576
        return {
            "x": _w((lambda *s: torch.randn(*s, dtype=torch.bfloat16) * 0.05)(B, S, D)),
            "wqkv": _w((lambda *s: torch.randn(*s, dtype=torch.bfloat16) * 0.8)(D, 3 * D)),
            "wo": _w((lambda *s: torch.randn(*s, dtype=torch.bfloat16) * 0.05)(D, D)),
        }
    _B_in = _B_setup()

    return {
        "A_q": _A_in["q"],
        "A_k": _A_in["k"],
        "A_v": _A_in["v"],
        "A_shift_k": _A_in["shift_k"],
        "A_ssm_k": _A_in["ssm_k"],
        "A_ssm_D": _A_in["ssm_D"],
        "B_x": _B_in["x"],
        "B_wqkv": _B_in["wqkv"],
        "B_wo": _B_in["wo"],
        "gate_w": _w((lambda *s: torch.randn(*s, dtype=torch.bfloat16) * 0.05)(576) * 16.0),
    }

def reference(A_q, A_k, A_v, A_shift_k, A_ssm_k, A_ssm_D, B_x, B_wqkv, B_wo, gate_w):
    def _A_ref(q, k, v, shift_k, ssm_k, ssm_D):
        B, S, D = q.shape
        ks = shift_k.shape[-1]
        k_pad = _pad(k, ((0, 0), (ks - 1, 0), (0, 0)))
        k_shift = torch.zeros_like(k)
        for t in range(ks):
            k_shift = k_shift + k_pad[:, t:t + S, :] * shift_k[:, ks - 1 - t][None, None, :]
        kv = k_shift * v
        L = 2 * S
        kv_pad = _pad(kv, ((0, 0), (0, S), (0, 0)))
        kf_pad = _pad(ssm_k, ((0, 0), (0, S)))
        kv_f = (lambda x, axes=(-2,-1): torch.fft.rfft2(x.float(), dim=axes))(kv_pad[:, None, :, :], axes=(1, 2))
        kf_f = (lambda x, axes=(-2,-1): torch.fft.rfft2(x.float(), dim=axes))(kf_pad[:, None, :], axes=(1, 2))
        kf_f = (lambda x, *d: x.permute(*d))(kf_f, 1, 2, 0)
        y_f = kv_f * kf_f[None, :, :, :]
        y = (lambda x, s, axes=(-2,-1): torch.fft.irfft2(x, s=s, dim=axes).to(torch.bfloat16))(y_f, (1, L), axes=(1, 2))[:, 0, :S, :]
        y = y + kv * ssm_D[None, None, :]
        return q * y

    def _B_ref(x, wqkv, wo):
        B, S, D = x.shape
        H = 32; Dh = D // H; W = 256
        qkv = (lambda x, *d: x.permute(*d))((x @ wqkv).reshape(B, S, 3, H, Dh), 2, 0, 3, 1, 4)
        q, k, v = qkv[0], qkv[1], qkv[2]
        scores = torch.einsum("bhqd,bhkd->bhqk", q, k) * (Dh ** -0.5)
        idx = torch.arange(S)
        mask = (idx[:, None] - idx[None, :] >= 0) & (idx[:, None] - idx[None, :] < W)
        scores = torch.where(mask[None, None], scores, -1e9)
        p = _softmax(scores, axis=-1)
        o = torch.einsum("bhqk,bhkd->bhqd", p, v)
        return (lambda x, *d: x.permute(*d))(o, 0, 2, 1, 3).reshape(B, S, D) @ wo

    x = A_q
    g = _sigmoid((x * gate_w).sum(-1, keepdims=True))
    a = _A_ref(x, A_k, A_v, A_shift_k, A_ssm_k, A_ssm_D)
    b = _B_ref(x, B_wqkv, B_wo)
    return g * a + (1 - g) * b
```

```cpp
#include <cuda_runtime.h>
#include <cuda_bf16.h>
#include <cuda.h>
#include <stdint.h>

namespace gm {

typedef __nv_bfloat16 bf16;

constexpr int SEQ = 2048;
constexpr int DM = 576;
constexpr int NCTA = 132;
constexpr int NTHREADS = 512;

constexpr int TROWS = 152;
constexpr int T_CTAS = 126;
constexpr int P2_CTAS = 128;

#define MCAST 0
#define DRY_L2 0
#define CONV_WAIT 0
#define MAP1 (MCAST ? 1 : 2)
#define MAP2 2
__device__ __forceinline__ int p1_mt(int c) { return MAP1 == 2 ? 3 * (c / 42) + c % 3 : MAP1 ? (c >> 1) % 9 : c % 9; }
__device__ __forceinline__ int p1_nt(int c) { return MAP1 == 2 ? (c % 42) / 3 : MAP1 ? 2 * ((c >> 1) / 9) + (c & 1) : c / 9; }
__device__ __forceinline__ int p2_hg(int c) { return MAP2 == 2 ? c / 16 : MAP2 ? (c >> 1) % 8 : c % 8; }
__device__ __forceinline__ int p2_rb(int c) { return MAP2 == 2 ? c % 16 : MAP2 ? 2 * ((c >> 1) / 8) + (c & 1) : c / 8; }

constexpr int P1_STAGE = 44032;
constexpr int P1_STAGES = 3;
constexpr int P2_Q = 0;
constexpr int P2_K = 18432;
constexpr int P2_V = 73728;
constexpr int P2_O = 129024;
constexpr int P3_STAGE = 28672;
constexpr int P3_STAGES = 5;
constexpr int C_OFF = 147456;
constexpr int P3_X = C_OFF;
constexpr int P3_Z = C_OFF + 19456;
constexpr int C_SLOT = 12672;
constexpr int C_E = 4352;
constexpr int C_O = 8512;
constexpr int PRE_K = C_OFF;
constexpr int PRE_V = C_OFF + 20480;
constexpr int PRE_ST = C_OFF + 39936;
constexpr int MISC_OFF = C_OFF + 5 * C_SLOT;
constexpr int ONES_OFF = MISC_OFF;
constexpr int GATE_OFF = MISC_OFF + 1024;
constexpr int DUMMY_OFF = GATE_OFF + 640;
constexpr int GSTG_OFF = DUMMY_OFF + 128;
constexpr int BAR_OFF = GSTG_OFF + 128;
constexpr int UNIT_CTR = BAR_OFF + 288;
constexpr int SMEM_USED = BAR_OFF + 352;
constexpr int SMEM_BYTES = SMEM_USED + 1024;

enum { B_P1_FULL = 0, B_P1_EMPTY = 3, B_XFREE1 = 6, B_KV = 7, B_XFREE2 = 11, B_P3_FULL = 12, B_P3_EMPTY = 17,
       B_P3_Z = 22, B_PRE = 23, B_CONV = 24, B_CONVD = 29, B_ODONE = 34, B_COUNT = 35 };

enum { M_P1 = 1, M_PRE = 2, M_CONV = 4, M_P2 = 8, M_P3 = 16, M_FUSED = 32 };

struct Params {
    CUtensorMap mW, mX152, mQ, mKV, mOst, mOld, mWo, mK160, mV152, mKvR, mZ, mOut;
    const bf16* x;
    const bf16* shift_k;
    const bf16* ssm_k;
    const bf16* ssm_D;
    const bf16* gate_w;
    const bf16* wqkv;
    const bf16* wo;
    int mode;
};

__device__ __align__(1024) bf16 g_qkvc[216 * SEQ * 8];
__device__ __align__(1024) bf16 g_oc[72 * SEQ * 8 + 2048];
constexpr int KVR_PITCH = SEQ + 128;
__device__ __align__(1024) bf16 g_kvR[DM * KVR_PITCH];
__device__ __align__(1024) bf16 g_zT[DM * SEQ];
__device__ __align__(1024) float g_gate[SEQ];
constexpr int CNT_P1 = 0, CNT_P2 = 16, CNT_PRE = 48, CNT_Z = 64, CNT_G = 80, CNT_EXTRA = 88, CNT_EXIT = 96, CNT_TOTAL = 128;
constexpr int CNT_STRIDE = 32;
__device__ unsigned int g_cnt[CNT_TOTAL * CNT_STRIDE];

#define FSTAMP(slot) do {} while (0)
#define TSTAMP(slot) do {} while (0)
#define TSTAMP_IF(cond, slot) do {} while (0)

__device__ __forceinline__ uint32_t smem_u32(const void* p) { return (uint32_t)__cvta_generic_to_shared(p); }
__device__ __forceinline__ void mbar_init(uint32_t bar, int cnt) {
    asm volatile("mbarrier.init.shared::cta.b64 [%0], %1;" ::"r"(bar), "r"(cnt) : "memory");
}
__device__ __forceinline__ void mbar_expect(uint32_t bar, int bytes) {
    asm volatile("mbarrier.arrive.expect_tx.shared::cta.b64 _, [%0], %1;" ::"r"(bar), "r"(bytes) : "memory");
}
__device__ __forceinline__ void mbar_arrive(uint32_t bar) {
    asm volatile("mbarrier.arrive.shared::cta.b64 _, [%0];" ::"r"(bar) : "memory");
}
__device__ __forceinline__ void mbar_wait(uint32_t bar, uint32_t parity) {
    uint32_t ok;
    int it = 0;
    while (true) {
        asm volatile("{\n.reg .pred p;\nmbarrier.try_wait.parity.shared::cta.b64 p, [%1], %2;\nselp.u32 %0, 1, 0, p;\n}"
                     : "=r"(ok) : "r"(bar), "r"(parity) : "memory");
        if (ok) break;
        if (++it > (1 << 20)) __trap();
    }
}
__device__ __forceinline__ bool mbar_test(uint32_t bar, uint32_t parity) {
    uint32_t ok;
    asm volatile("{\n.reg .pred p;\nmbarrier.test_wait.parity.shared::cta.b64 p, [%1], %2;\nselp.u32 %0, 1, 0, p;\n}"
                 : "=r"(ok) : "r"(bar), "r"(parity) : "memory");
    return ok != 0;
}
__device__ __forceinline__ void tma_load2d(uint32_t dst, const CUtensorMap* m, int x, int y, uint32_t bar) {
    asm volatile("cp.async.bulk.tensor.2d.shared::cluster.global.mbarrier::complete_tx::bytes [%0], [%1, {%3, %4}], [%2];"
                 ::"r"(dst), "l"(m), "r"(bar), "r"(x), "r"(y) : "memory");
}
__device__ __forceinline__ void tma_load3d(uint32_t dst, const CUtensorMap* m, int x, int y, int z, uint32_t bar) {
    asm volatile("cp.async.bulk.tensor.3d.shared::cluster.global.mbarrier::complete_tx::bytes [%0], [%1, {%3, %4, %5}], [%2];"
                 ::"r"(dst), "l"(m), "r"(bar), "r"(x), "r"(y), "r"(z) : "memory");
}
__device__ __forceinline__ void tma_load3d_mc(uint32_t dst, const CUtensorMap* m, int x, int y, int z, uint32_t bar, uint16_t mask) {
    asm volatile("cp.async.bulk.tensor.3d.shared::cluster.global.mbarrier::complete_tx::bytes.multicast::cluster [%0], [%1, {%3, %4, %5}], [%2], %6;"
                 ::"r"(dst), "l"(m), "r"(bar), "r"(x), "r"(y), "r"(z), "h"(mask) : "memory");
}
__device__ __forceinline__ void mbar_arrive_peer(uint32_t bar, uint32_t peer) {
    asm volatile("{\n.reg .b32 ra;\nmapa.shared::cluster.u32 ra, %0, %1;\nmbarrier.arrive.release.cluster.shared::cluster.b64 _, [ra];\n}"
                 ::"r"(bar), "r"(peer) : "memory");
}
__device__ __forceinline__ void tma_store2d(const CUtensorMap* m, int x, int y, uint32_t src) {
    asm volatile("cp.async.bulk.tensor.2d.global.shared::cta.bulk_group [%0, {%2, %3}], [%1];"
                 ::"l"(m), "r"(src), "r"(x), "r"(y) : "memory");
}
__device__ __forceinline__ void bulk_load(uint32_t dst, const void* src, int bytes, uint32_t bar) {
    asm volatile("cp.async.bulk.shared::cluster.global.mbarrier::complete_tx::bytes [%0], [%1], %2, [%3];"
                 ::"r"(dst), "l"(src), "r"(bytes), "r"(bar) : "memory");
}
__device__ __forceinline__ void bulk_store(void* dst, uint32_t src, int bytes) {
    asm volatile("cp.async.bulk.global.shared::cta.bulk_group [%0], [%1], %2;" ::"l"(dst), "r"(src), "r"(bytes) : "memory");
}
__device__ __forceinline__ void l2_prefetch(const void* src, int bytes) {
    asm volatile("cp.async.bulk.prefetch.L2.global [%0], %1;" ::"l"(src), "r"(bytes) : "memory");
}
__device__ __forceinline__ void bulk_commit() { asm volatile("cp.async.bulk.commit_group;" ::: "memory"); }
__device__ __forceinline__ void bulk_wait0() { asm volatile("cp.async.bulk.wait_group 0;" ::: "memory"); }
__device__ __forceinline__ void fence_async_smem() { asm volatile("fence.proxy.async.shared::cta;" ::: "memory"); }
__device__ __forceinline__ void prefetch_tmap(const CUtensorMap* m) {
    asm volatile("prefetch.tensormap [%0];" ::"l"(m) : "memory");
}
__device__ __forceinline__ void bar_sync(int id, int n) { asm volatile("bar.sync %0, %1;" ::"r"(id), "r"(n) : "memory"); }
__device__ __forceinline__ bool bar_red_or(int id, int n, bool v) {
    uint32_t r;
    asm volatile("{\n.reg .pred p, q;\nsetp.ne.u32 q, %3, 0;\nbar.red.or.pred p, %1, %2, q;\nselp.u32 %0, 1, 0, p;\n}"
                 : "=r"(r) : "r"(id), "r"(n), "r"((uint32_t)v) : "memory");
    return r != 0;
}
__device__ __forceinline__ void signal_add(int idx) {
    asm volatile("red.relaxed.gpu.global.add.u32 [%0], 1;" ::"l"(&g_cnt[idx * CNT_STRIDE]) : "memory");
}
__device__ __forceinline__ void wait_counter(int idx, unsigned target) {
    unsigned v;
    int it = 0;
    while (true) {
        asm volatile("ld.relaxed.gpu.global.u32 %0, [%1];" : "=r"(v) : "l"(&g_cnt[idx * CNT_STRIDE]) : "memory");
        if (v >= target) break;
        if (++it > (1 << 22)) __trap();
    }
}
__device__ __forceinline__ void wait_counters(int idx, int n, unsigned target) {
    int it = 0;
    while (true) {
        unsigned v0, v1, v2, v3;
        asm volatile("ld.relaxed.gpu.global.u32 %0, [%1];" : "=r"(v0) : "l"(&g_cnt[idx * CNT_STRIDE]) : "memory");
        asm volatile("ld.relaxed.gpu.global.u32 %0, [%1];" : "=r"(v1) : "l"(&g_cnt[(idx + (n > 1 ? 1 : 0)) * CNT_STRIDE]) : "memory");
        asm volatile("ld.relaxed.gpu.global.u32 %0, [%1];" : "=r"(v2) : "l"(&g_cnt[(idx + (n > 2 ? 2 : 0)) * CNT_STRIDE]) : "memory");
        asm volatile("ld.relaxed.gpu.global.u32 %0, [%1];" : "=r"(v3) : "l"(&g_cnt[(idx + (n > 3 ? 3 : 0)) * CNT_STRIDE]) : "memory");
        if (min(min(v0, v1), min(v2, v3)) >= target) break;
        if (++it > (1 << 22)) __trap();
    }
}
__device__ __forceinline__ void wg_fence() { asm volatile("wgmma.fence.sync.aligned;" ::: "memory"); }
__device__ __forceinline__ void wg_commit() { asm volatile("wgmma.commit_group.sync.aligned;" ::: "memory"); }
template <int N> __device__ __forceinline__ void wg_wait() {
    asm volatile("wgmma.wait_group.sync.aligned %0;" ::"n"(N) : "memory");
}
template <int N> __device__ __forceinline__ void pin(float (&r)[N]) {
#pragma unroll
    for (int i = 0; i < N; i++) asm volatile("" : "+f"(r[i])::"memory");
}
__device__ __forceinline__ uint64_t make_desc(uint32_t addr, uint32_t lbo, uint32_t sbo, int swz) {
    return (uint64_t)((addr & 0x3FFFF) >> 4) | ((uint64_t)(lbo >> 4) << 16) | ((uint64_t)(sbo >> 4) << 32) |
           ((uint64_t)swz << 62);
}
__device__ __forceinline__ void ldsm_x4(uint32_t (&r)[4], uint32_t addr) {
    asm volatile("ldmatrix.sync.aligned.m8n8.x4.shared.b16 {%0,%1,%2,%3}, [%4];"
                 : "=r"(r[0]), "=r"(r[1]), "=r"(r[2]), "=r"(r[3]) : "r"(addr) : "memory");
}
__device__ __forceinline__ void ldsm_x2(uint32_t& r0, uint32_t& r1, uint32_t addr) {
    asm volatile("ldmatrix.sync.aligned.m8n8.x2.shared.b16 {%0,%1}, [%2];" : "=r"(r0), "=r"(r1) : "r"(addr) : "memory");
}
__device__ __forceinline__ void ldsm_x4_t(uint32_t (&r)[4], uint32_t addr) {
    asm volatile("ldmatrix.sync.aligned.m8n8.x4.trans.shared.b16 {%0,%1,%2,%3}, [%4];"
                 : "=r"(r[0]), "=r"(r[1]), "=r"(r[2]), "=r"(r[3]) : "r"(addr) : "memory");
}
__device__ __forceinline__ void ldsm_x2_t(uint32_t& r0, uint32_t& r1, uint32_t addr) {
    asm volatile("ldmatrix.sync.aligned.m8n8.x2.trans.shared.b16 {%0,%1}, [%2];" : "=r"(r0), "=r"(r1) : "r"(addr) : "memory");
}
__device__ __forceinline__ void stsm_x4_t(uint32_t addr, uint32_t r0, uint32_t r1, uint32_t r2, uint32_t r3) {
    asm volatile("stmatrix.sync.aligned.m8n8.x4.trans.shared.b16 [%0], {%1,%2,%3,%4};"
                 ::"r"(addr), "r"(r0), "r"(r1), "r"(r2), "r"(r3) : "memory");
}
__device__ __forceinline__ void stsm_x2_t(uint32_t addr, uint32_t r0, uint32_t r1) {
    asm volatile("stmatrix.sync.aligned.m8n8.x2.trans.shared.b16 [%0], {%1,%2};" ::"r"(addr), "r"(r0), "r"(r1) : "memory");
}
__device__ __forceinline__ uint32_t lds32(uint32_t addr) {
    uint32_t v;
    asm volatile("ld.shared.u32 %0, [%1];" : "=r"(v) : "r"(addr) : "memory");
    return v;
}
__device__ __forceinline__ void sts32(uint32_t addr, uint32_t v) {
    asm volatile("st.shared.u32 [%0], %1;" ::"r"(addr), "r"(v) : "memory");
}
__device__ __forceinline__ void sts128(uint32_t addr, uint32_t a, uint32_t b, uint32_t c, uint32_t d) {
    asm volatile("st.shared.v4.u32 [%0], {%1,%2,%3,%4};" ::"r"(addr), "r"(a), "r"(b), "r"(c), "r"(d) : "memory");
}
__device__ __forceinline__ uint32_t pack_bf16(float lo, float hi) {
    uint32_t r;
    asm("cvt.rn.bf16x2.f32 %0, %1, %2;" : "=r"(r) : "f"(hi), "f"(lo));
    return r;
}
__device__ __forceinline__ float bf_lo(uint32_t v) { return __uint_as_float(v << 16); }
__device__ __forceinline__ float bf_hi(uint32_t v) { return __uint_as_float(v & 0xffff0000u); }
__device__ __forceinline__ float rbf(float x) { return __bfloat162float(__float2bfloat16_rn(x)); }
__device__ __forceinline__ uint32_t hmul2(uint32_t a, uint32_t b) {
    uint32_t r;
    asm("mul.rn.bf16x2 %0, %1, %2;" : "=r"(r) : "r"(a), "r"(b));
    return r;
}
__device__ __forceinline__ uint32_t hadd2(uint32_t a, uint32_t b) {
    uint32_t r;
    asm("add.rn.bf16x2 %0, %1, %2;" : "=r"(r) : "r"(a), "r"(b));
    return r;
}
__device__ __forceinline__ uint32_t hsub2(uint32_t a, uint32_t b) {
    uint32_t r;
    asm("sub.rn.bf16x2 %0, %1, %2;" : "=r"(r) : "r"(a), "r"(b));
    return r;
}
__device__ __forceinline__ float ex2(float x) {
    float r;
    asm("ex2.approx.ftz.f32 %0, %1;" : "=f"(r) : "f"(x));
    return r;
}
__device__ __forceinline__ void bar_arrive(int id, int n) { asm volatile("bar.arrive %0, %1;" ::"r"(id), "r"(n) : "memory"); }
__device__ __forceinline__ void mma16816(float (&c)[4], const uint32_t (&a)[4], uint32_t b0, uint32_t b1) {
    asm("mma.sync.aligned.m16n8k16.row.col.f32.bf16.bf16.f32 {%0,%1,%2,%3},{%4,%5,%6,%7},{%8,%9},{%0,%1,%2,%3};"
        : "+f"(c[0]), "+f"(c[1]), "+f"(c[2]), "+f"(c[3])
        : "r"(a[0]), "r"(a[1]), "r"(a[2]), "r"(a[3]), "r"(b0), "r"(b1));
}
__device__ __forceinline__ void mma16816c(float (&d)[4], const uint32_t (&a)[4], uint32_t b0, uint32_t b1, const float (&c)[4]) {
    asm("mma.sync.aligned.m16n8k16.row.col.f32.bf16.bf16.f32 {%0,%1,%2,%3},{%4,%5,%6,%7},{%8,%9},{%10,%11,%12,%13};"
        : "=f"(d[0]), "=f"(d[1]), "=f"(d[2]), "=f"(d[3])
        : "r"(a[0]), "r"(a[1]), "r"(a[2]), "r"(a[3]), "r"(b0), "r"(b1), "f"(c[0]), "f"(c[1]), "f"(c[2]), "f"(c[3]));
}
__device__ __forceinline__ void mma16816v(float (&c)[4], const uint32_t (&a)[4], uint32_t b0, uint32_t b1) {
    asm volatile("mma.sync.aligned.m16n8k16.row.col.f32.bf16.bf16.f32 {%0,%1,%2,%3},{%4,%5,%6,%7},{%8,%9},{%0,%1,%2,%3};"
        : "+f"(c[0]), "+f"(c[1]), "+f"(c[2]), "+f"(c[3])
        : "r"(a[0]), "r"(a[1]), "r"(a[2]), "r"(a[3]), "r"(b0), "r"(b1));
}
__device__ __forceinline__ void mma1688(float (&c)[4], uint32_t a0, uint32_t a1, uint32_t b0) {
    asm("mma.sync.aligned.m16n8k8.row.col.f32.bf16.bf16.f32 {%0,%1,%2,%3},{%4,%5},{%6},{%0,%1,%2,%3};"
        : "+f"(c[0]), "+f"(c[1]), "+f"(c[2]), "+f"(c[3]) : "r"(a0), "r"(a1), "r"(b0));
}

template <int HI>
__device__ __forceinline__ void wgmma_rs_init_n64_t0(float (&d)[32], const uint32_t (&a)[4], uint32_t lo) {
  asm volatile("{\n.reg .b64 dd;\n.reg .b32 hh;\nmov.b32 hh, %37;\nmov.b64 dd, {%36, hh};\n"
    "wgmma.mma_async.sync.aligned.m64n64k16.f32.bf16.bf16 {%0,%1,%2,%3,%4,%5,%6,%7,%8,%9,%10,%11,%12,%13,%14,%15,%16,%17,%18,%19,%20,%21,%22,%23,%24,%25,%26,%27,%28,%29,%30,%31}, {%32,%33,%34,%35}, dd, 0, 1, 1, 0;\n}\n"
    : "=f"(d[0]), "=f"(d[1]), "=f"(d[2]), "=f"(d[3]), "=f"(d[4]), "=f"(d[5]), "=f"(d[6]), "=f"(d[7]), "=f"(d[8]), "=f"(d[9]), "=f"(d[10]), "=f"(d[11]), "=f"(d[12]), "=f"(d[13]), "=f"(d[14]), "=f"(d[15]), "=f"(d[16]), "=f"(d[17]), "=f"(d[18]), "=f"(d[19]), "=f"(d[20]), "=f"(d[21]), "=f"(d[22]), "=f"(d[23]), "=f"(d[24]), "=f"(d[25]), "=f"(d[26]), "=f"(d[27]), "=f"(d[28]), "=f"(d[29]), "=f"(d[30]), "=f"(d[31])
    : "r"(a[0]), "r"(a[1]), "r"(a[2]), "r"(a[3]), "r"(lo), "n"(HI));
}
template <int HI>
__device__ __forceinline__ void wgmma_rs_init_n24_t1(float (&d)[12], const uint32_t (&a)[4], uint32_t lo) {
  asm volatile("{\n.reg .b64 dd;\n.reg .b32 hh;\nmov.b32 hh, %17;\nmov.b64 dd, {%16, hh};\n"
    "wgmma.mma_async.sync.aligned.m64n24k16.f32.bf16.bf16 {%0,%1,%2,%3,%4,%5,%6,%7,%8,%9,%10,%11}, {%12,%13,%14,%15}, dd, 0, 1, 1, 1;\n}\n"
    : "=f"(d[0]), "=f"(d[1]), "=f"(d[2]), "=f"(d[3]), "=f"(d[4]), "=f"(d[5]), "=f"(d[6]), "=f"(d[7]), "=f"(d[8]), "=f"(d[9]), "=f"(d[10]), "=f"(d[11])
    : "r"(a[0]), "r"(a[1]), "r"(a[2]), "r"(a[3]), "r"(lo), "n"(HI));
}
__device__ __forceinline__ void wgmma_ss_n152_t10(float (&d)[76], uint64_t da, uint64_t db, int scale_d) {
  asm volatile("{\n.reg .pred p;\nsetp.ne.b32 p, %78, 0;\n"
    "wgmma.mma_async.sync.aligned.m64n152k16.f32.bf16.bf16 {%0,%1,%2,%3,%4,%5,%6,%7,%8,%9,%10,%11,%12,%13,%14,%15,%16,%17,%18,%19,%20,%21,%22,%23,%24,%25,%26,%27,%28,%29,%30,%31,%32,%33,%34,%35,%36,%37,%38,%39,%40,%41,%42,%43,%44,%45,%46,%47,%48,%49,%50,%51,%52,%53,%54,%55,%56,%57,%58,%59,%60,%61,%62,%63,%64,%65,%66,%67,%68,%69,%70,%71,%72,%73,%74,%75}, %76, %77, p, 1, 1, 1, 0;\n}\n"
    : "+f"(d[0]), "+f"(d[1]), "+f"(d[2]), "+f"(d[3]), "+f"(d[4]), "+f"(d[5]), "+f"(d[6]), "+f"(d[7]), "+f"(d[8]), "+f"(d[9]), "+f"(d[10]), "+f"(d[11]), "+f"(d[12]), "+f"(d[13]), "+f"(d[14]), "+f"(d[15]), "+f"(d[16]), "+f"(d[17]), "+f"(d[18]), "+f"(d[19]), "+f"(d[20]), "+f"(d[21]), "+f"(d[22]), "+f"(d[23]), "+f"(d[24]), "+f"(d[25]), "+f"(d[26]), "+f"(d[27]), "+f"(d[28]), "+f"(d[29]), "+f"(d[30]), "+f"(d[31]), "+f"(d[32]), "+f"(d[33]), "+f"(d[34]), "+f"(d[35]), "+f"(d[36]), "+f"(d[37]), "+f"(d[38]), "+f"(d[39]), "+f"(d[40]), "+f"(d[41]), "+f"(d[42]), "+f"(d[43]), "+f"(d[44]), "+f"(d[45]), "+f"(d[46]), "+f"(d[47]), "+f"(d[48]), "+f"(d[49]), "+f"(d[50]), "+f"(d[51]), "+f"(d[52]), "+f"(d[53]), "+f"(d[54]), "+f"(d[55]), "+f"(d[56]), "+f"(d[57]), "+f"(d[58]), "+f"(d[59]), "+f"(d[60]), "+f"(d[61]), "+f"(d[62]), "+f"(d[63]), "+f"(d[64]), "+f"(d[65]), "+f"(d[66]), "+f"(d[67]), "+f"(d[68]), "+f"(d[69]), "+f"(d[70]), "+f"(d[71]), "+f"(d[72]), "+f"(d[73]), "+f"(d[74]), "+f"(d[75])
    : "l"(da), "l"(db), "r"(scale_d));
}
template <int HI, int SCALE_D>
__device__ __forceinline__ void wgmma_rs_n64_t0(float (&d)[32], const uint32_t (&a)[4], uint32_t lo) {
  asm volatile("{\n.reg .b64 dd;\n.reg .b32 hh;\nmov.b32 hh, %37;\nmov.b64 dd, {%36, hh};\n"
    "wgmma.mma_async.sync.aligned.m64n64k16.f32.bf16.bf16 {%0,%1,%2,%3,%4,%5,%6,%7,%8,%9,%10,%11,%12,%13,%14,%15,%16,%17,%18,%19,%20,%21,%22,%23,%24,%25,%26,%27,%28,%29,%30,%31}, {%32,%33,%34,%35}, dd, %38, 1, 1, 0;\n}\n"
    : "+f"(d[0]), "+f"(d[1]), "+f"(d[2]), "+f"(d[3]), "+f"(d[4]), "+f"(d[5]), "+f"(d[6]), "+f"(d[7]), "+f"(d[8]), "+f"(d[9]), "+f"(d[10]), "+f"(d[11]), "+f"(d[12]), "+f"(d[13]), "+f"(d[14]), "+f"(d[15]), "+f"(d[16]), "+f"(d[17]), "+f"(d[18]), "+f"(d[19]), "+f"(d[20]), "+f"(d[21]), "+f"(d[22]), "+f"(d[23]), "+f"(d[24]), "+f"(d[25]), "+f"(d[26]), "+f"(d[27]), "+f"(d[28]), "+f"(d[29]), "+f"(d[30]), "+f"(d[31])
    : "r"(a[0]), "r"(a[1]), "r"(a[2]), "r"(a[3]), "r"(lo), "n"(HI), "n"(SCALE_D));
}
template <int HI, int SCALE_D>
__device__ __forceinline__ void wgmma_rs_n24_t1(float (&d)[12], const uint32_t (&a)[4], uint32_t lo) {
  asm volatile("{\n.reg .b64 dd;\n.reg .b32 hh;\nmov.b32 hh, %17;\nmov.b64 dd, {%16, hh};\n"
    "wgmma.mma_async.sync.aligned.m64n24k16.f32.bf16.bf16 {%0,%1,%2,%3,%4,%5,%6,%7,%8,%9,%10,%11}, {%12,%13,%14,%15}, dd, %18, 1, 1, 1;\n}\n"
    : "+f"(d[0]), "+f"(d[1]), "+f"(d[2]), "+f"(d[3]), "+f"(d[4]), "+f"(d[5]), "+f"(d[6]), "+f"(d[7]), "+f"(d[8]), "+f"(d[9]), "+f"(d[10]), "+f"(d[11])
    : "r"(a[0]), "r"(a[1]), "r"(a[2]), "r"(a[3]), "r"(lo), "n"(HI), "n"(SCALE_D));
}
__device__ __forceinline__ void wgmma_ss_n80_t10(float (&d)[40], uint64_t da, uint64_t db, int scale_d) {
  asm volatile("{\n.reg .pred p;\nsetp.ne.b32 p, %42, 0;\n"
    "wgmma.mma_async.sync.aligned.m64n80k16.f32.bf16.bf16 {%0,%1,%2,%3,%4,%5,%6,%7,%8,%9,%10,%11,%12,%13,%14,%15,%16,%17,%18,%19,%20,%21,%22,%23,%24,%25,%26,%27,%28,%29,%30,%31,%32,%33,%34,%35,%36,%37,%38,%39}, %40, %41, p, 1, 1, 1, 0;\n}\n"
    : "+f"(d[0]), "+f"(d[1]), "+f"(d[2]), "+f"(d[3]), "+f"(d[4]), "+f"(d[5]), "+f"(d[6]), "+f"(d[7]), "+f"(d[8]), "+f"(d[9]), "+f"(d[10]), "+f"(d[11]), "+f"(d[12]), "+f"(d[13]), "+f"(d[14]), "+f"(d[15]), "+f"(d[16]), "+f"(d[17]), "+f"(d[18]), "+f"(d[19]), "+f"(d[20]), "+f"(d[21]), "+f"(d[22]), "+f"(d[23]), "+f"(d[24]), "+f"(d[25]), "+f"(d[26]), "+f"(d[27]), "+f"(d[28]), "+f"(d[29]), "+f"(d[30]), "+f"(d[31]), "+f"(d[32]), "+f"(d[33]), "+f"(d[34]), "+f"(d[35]), "+f"(d[36]), "+f"(d[37]), "+f"(d[38]), "+f"(d[39])
    : "l"(da), "l"(db), "r"(scale_d));
}

constexpr float SM_SCALE_LOG2 = 0.23570226039551584f * 1.4426950408889634f;

__device__ __forceinline__ void p1_load(const Params& p, uint32_t sb, int mt, int nt, int kb) {
    const int s = kb % P1_STAGES;
    const uint32_t full = sb + BAR_OFF + 8 * (B_P1_FULL + s), st = sb + s * P1_STAGE;
    mbar_expect(full, P1_STAGE);
    tma_load2d(st + 24576, &p.mX152, kb * 64, nt * TROWS, full);
    tma_load3d(st, &p.mW, 0, kb * 64, 3 * mt, full);
}
__device__ __forceinline__ void p2_loads(const Params& p, uint32_t sb, int c) {
    const uint32_t bars = sb + BAR_OFF;
    const int hg = p2_hg(c), rb = p2_rb(c);
    if (p.mode & M_FUSED) {
        const int r0 = max(0, 128 * rb - 256), r1 = 128 * rb + 127;
        wait_counters(CNT_P1 + r0 / TROWS, r1 / TROWS - r0 / TROWS + 1, 27);
    }
    TSTAMP(5);
    const int row0 = 128 * rb - 256, kc = 72 + 9 * hg, vc = 144 + 9 * hg;
    const int blk0 = 2 * rb - 4;
    mbar_expect(bars + 8 * B_KV, 18432 + 2 * 9216);
    tma_load2d(sb + P2_Q, &p.mQ, 2 * (row0 + 256), 9 * hg, bars + 8 * B_KV);
    tma_load3d(sb + P2_K + 4 * 9216, &p.mKV, 0, kc, blk0 + 4, bars + 8 * B_KV);
    for (int s = 1; s < 4; s++) {
        const int vb = 6 - 2 * s, kb = 4 - 2 * s;
        const uint32_t bar = bars + 8 * (B_KV + s);
        mbar_expect(bar, (s < 3 ? 4 : 2) * 9216);
        if (s < 3) tma_load3d(sb + P2_K + kb * 9216, &p.mKV, 0, kc, blk0 + kb, bar);
        tma_load3d(sb + P2_V + vb * 9216, &p.mKV, 0, vc, blk0 + vb, bar);
    }
}
__device__ __forceinline__ void p3_load_o(const Params& p, uint32_t sb, int t0, int kb) {
    const int s = kb % P3_STAGES;
    const uint32_t full = sb + BAR_OFF + 8 * (B_P3_FULL + s), st = sb + s * P3_STAGE;
    tma_load3d(st + 8192, &p.mOld, 2 * t0, 0, kb * 8, full);
}
__device__ __forceinline__ void p3_load_w(const Params& p, uint32_t sb, int dt, int kb) {
    const int s = kb % P3_STAGES;
    const uint32_t full = sb + BAR_OFF + 8 * (B_P3_FULL + s), st = sb + s * P3_STAGE;
    mbar_expect(full, P3_STAGE);
    tma_load2d(st, &p.mWo, dt * 64, kb * 64, full);
}

__device__ __forceinline__ void phase1(const Params& p, uint32_t sb, int c, int wg, int tid) {
    const uint32_t bars = sb + BAR_OFF;
    const int mt = p1_mt(c), nt = p1_nt(c);
    const int lane = tid & 31, w = (tid >> 5) & 3;
    const bool real = c < T_CTAS;
    float acc[76];
    if (!real) {
#pragma unroll
        for (int k = 0; k < 76; k++) acc[k] = 0.f;
    } else {
    const uint64_t da0 = make_desc(sb + wg * (MCAST ? 4096 : 8192), 1024, 1024, 1), db0 = make_desc(sb + 24576, 16, 1024, 1);
#pragma unroll 1
    for (int kq = 0; kq < 3; kq++) {
#pragma unroll
        for (int s = 0; s < P1_STAGES; s++) {
            const int kb = 3 * kq + s;
            mbar_wait(bars + 8 * (B_P1_FULL + s), kq & 1);
            TSTAMP_IF(tid == 0 && kb == 0, 1);
            wg_fence();
#pragma unroll
            for (int k = 0; k < 4; k++)
                wgmma_ss_n152_t10(acc, da0 + (s * (P1_STAGE >> 4) + (MCAST ? (k >> 1) * 768 + (k & 1) * 128 : k * 128)),
                                  db0 + (s * (P1_STAGE >> 4) + k * 2), (kb | k) != 0);
            wg_commit();
            wg_wait<1>();
            if (kb > 0 && kb + 2 < 9) {
                const int ps = (s + 2) % P1_STAGES;
                if (tid == 128 || tid == 256) mbar_arrive(bars + 8 * (B_P1_EMPTY + ps));
                if (tid == 0) {
                    mbar_wait(bars + 8 * (B_P1_EMPTY + ps), ((kb - 1) / P1_STAGES) & 1);
                    p1_load(p, sb, mt, nt, kb + 2);
                }
                __syncwarp();
            }
        }
    }
    wg_wait<0>();
    pin(acc);
    TSTAMP_IF(tid == 0, 2);
    bar_sync(1, 384);
    }
    const int atom = 3 * mt + wg;
    const float sc = (atom < 9) ? SM_SCALE_LOG2 : 1.f;
    const uint32_t stg = sb + wg * (8 * TROWS * 16);
    const uint32_t laddr = real ? stg + ((2 * w + ((lane >> 3) & 1)) * TROWS + (lane >> 4) * 8 + (lane & 7)) * 16
                                : sb + P2_O + (lane & 7) * 16 + (lane >> 4) * 128;
#pragma unroll
    for (int j = 0; j < 18; j += 2) {
        stsm_x4_t(laddr + j * 128, pack_bf16(acc[4 * j] * sc, acc[4 * j + 1] * sc), pack_bf16(acc[4 * j + 2] * sc, acc[4 * j + 3] * sc),
                  pack_bf16(acc[4 * j + 4] * sc, acc[4 * j + 5] * sc), pack_bf16(acc[4 * j + 6] * sc, acc[4 * j + 7] * sc));
    }
    stsm_x2_t(laddr + 18 * 128 - ((lane >> 4) * 128), pack_bf16(acc[72] * sc, acc[73] * sc), pack_bf16(acc[74] * sc, acc[75] * sc));
    fence_async_smem();
    bar_sync(2 + wg, 128);
    if (real && tid % 128 == 0) {
        const int t0 = nt * TROWS;
        const int nrows = min(TROWS, SEQ - t0);
        for (int cl = 0; cl < 8; cl++)
            bulk_store(g_qkvc + ((size_t)(atom * 8 + cl) * SEQ + t0) * 8, stg + cl * TROWS * 16, nrows * 16);
        bulk_commit();
        bulk_wait0();
        TSTAMP_IF(tid == 0, 3);
        if (p.mode & M_FUSED) signal_add(CNT_P1 + nt);
        mbar_arrive(bars + 8 * B_XFREE1);
    }
    __syncwarp();
}

#define STAGGER 0
__device__ __forceinline__ void wg_S(float (&s)[32], const uint32_t (&q0)[4], const uint32_t (&q1)[4], uint32_t kd, uint32_t lb1, int j) {
    wgmma_rs_n64_t0<8, 0>(s, q0, kd + j * 576 + (64u << 16));
    wgmma_rs_n64_t0<8, 1>(s, q1, kd + j * 576 + 128 + lb1 - ((uint32_t)(j * 576) << 16));
}
template <int FIRST>
__device__ __forceinline__ void wg_PV(float (&o)[12], const uint32_t (&pp)[4][4], uint32_t vd, int j) {
    wgmma_rs_n24_t1<64, !FIRST>(o, pp[0], vd + j * 576);
#pragma unroll
    for (int k = 1; k < 4; k++) wgmma_rs_n24_t1<64, 1>(o, pp[k], vd + j * 576 + k * 16);
}
template <int K>
__device__ __forceinline__ void exp_full(const float (&s)[32], uint32_t (&pp)[4][4], float& l0, float& l1) {
    float e[8];
#pragma unroll
    for (int u = 0; u < 8; u++) e[u] = ex2(s[8 * K + u]);
    l0 += (e[0] + e[1]) + (e[4] + e[5]);
    l1 += (e[2] + e[3]) + (e[6] + e[7]);
    pp[K][0] = pack_bf16(e[0], e[1]); pp[K][1] = pack_bf16(e[2], e[3]); pp[K][2] = pack_bf16(e[4], e[5]); pp[K][3] = pack_bf16(e[6], e[7]);
}
template <int K>
__device__ __forceinline__ void zero_grp(uint32_t (&pp)[4][4]) { pp[K][0] = pp[K][1] = pp[K][2] = pp[K][3] = 0u; }
template <int W>
__device__ __forceinline__ void diag_chunk(float (&s)[32], uint32_t (&pp)[4][4], bool k0, bool k1, float& l0, float& l1, uint32_t& nm) {
    const float* d = &s[8 * W];
    float m0 = fmaxf(k0 ? d[0] : -INFINITY, k1 ? d[1] : -INFINITY);
    float m1 = fmaxf(fmaxf(d[2], d[3]), fmaxf(k0 ? d[6] : -INFINITY, k1 ? d[7] : -INFINITY));
    m0 = fmaxf(m0, __shfl_xor_sync(0xffffffffu, m0, 1));
    m1 = fmaxf(m1, __shfl_xor_sync(0xffffffffu, m1, 1));
    m0 = fmaxf(m0, __shfl_xor_sync(0xffffffffu, m0, 2));
    m1 = fmaxf(m1, __shfl_xor_sync(0xffffffffu, m1, 2));
    nm = pack_bf16(-m0, -m1);
    const float n0 = bf_lo(nm), n1 = bf_hi(nm);
#pragma unroll
    for (int u = 0; u < 8 * (W + 1); u++) s[u] += (u & 2) ? n1 : n0;
    if (W > 0) exp_full<0>(s, pp, l0, l1); else zero_grp<0>(pp);
    if (W > 1) exp_full<1>(s, pp, l0, l1); else zero_grp<1>(pp);
    if (W > 2) exp_full<2>(s, pp, l0, l1); else zero_grp<2>(pp);
    zero_grp<3>(pp);
    const float p0 = k0 ? ex2(d[0]) : 0.f, p1 = k1 ? ex2(d[1]) : 0.f, p2 = ex2(d[2]), p3 = ex2(d[3]);
    const float p6 = k0 ? ex2(d[6]) : 0.f, p7 = k1 ? ex2(d[7]) : 0.f;
    l0 += p0 + p1;
    l1 += (p2 + p3) + (p6 + p7);
    pp[W][0] = pack_bf16(p0, p1); pp[W][1] = pack_bf16(p2, p3); pp[W][2] = 0u; pp[W][3] = pack_bf16(p6, p7);
}
template <int W>
__device__ __forceinline__ void edge_chunk(const float (&s)[32], uint32_t (&pp)[4][4], bool k0, bool k1, float& l0, float& l1) {
    zero_grp<0>(pp);
    if (W < 1) exp_full<1>(s, pp, l0, l1); else zero_grp<1>(pp);
    if (W < 2) exp_full<2>(s, pp, l0, l1); else zero_grp<2>(pp);
    if (W < 3) exp_full<3>(s, pp, l0, l1); else zero_grp<3>(pp);
    const float* d = &s[8 * W];
    const float p0 = k0 ? 0.f : ex2(d[0]), p1 = k1 ? 0.f : ex2(d[1]), p4 = ex2(d[4]), p5 = ex2(d[5]);
    const float p6 = k0 ? 0.f : ex2(d[6]), p7 = k1 ? 0.f : ex2(d[7]);
    l0 += (p0 + p1) + (p4 + p5);
    l1 += p6 + p7;
    pp[W][0] = pack_bf16(p0, p1); pp[W][1] = 0u; pp[W][2] = pack_bf16(p4, p5); pp[W][3] = pack_bf16(p6, p7);
}

struct KFrag { uint32_t f[4], g0, g1; };
__device__ __forceinline__ uint32_t key_off(int key) { return key * 16 + (key >> 6) * 8192; }
__device__ __forceinline__ void load_k(KFrag& k, uint32_t kA, uint32_t kB, uint32_t off) {
    ldsm_x4(k.f, kA + off);
    ldsm_x2(k.g0, k.g1, kB + off);
}
__device__ __forceinline__ void load_v(KFrag& v, uint32_t vA, uint32_t kB, uint32_t off) {
    ldsm_x4_t(v.f, vA + off);
    ldsm_x2_t(v.g0, v.g1, kB + off + (P2_V - P2_K));
}
__device__ __forceinline__ void s_mma(float (&d)[8], const uint32_t (&q0)[4], const uint32_t (&q1)[2], const KFrag& k, const float (&c)[4]) {
    float (&d0)[4] = *reinterpret_cast<float (*)[4]>(&d[0]);
    float (&d1)[4] = *reinterpret_cast<float (*)[4]>(&d[4]);
    mma16816c(d0, q0, k.f[0], k.f[1], c);
    mma16816c(d1, q0, k.f[2], k.f[3], c);
    mma1688(d0, q1[0], q1[1], k.g0);
    mma1688(d1, q1[0], q1[1], k.g1);
}
__device__ __forceinline__ void pv_mma(float (&o)[3][4], const uint32_t (&pa)[4], const KFrag& v) {
    mma16816(o[0], pa, v.f[0], v.f[1]);
    mma16816(o[1], pa, v.f[2], v.f[3]);
    mma16816(o[2], pa, v.g0, v.g1);
}
__device__ __forceinline__ void exp_block(uint32_t (&pa)[4], const float (&s)[8], float& l0, float& l1) {
    float e[8];
#pragma unroll
    for (int k = 0; k < 8; k++) e[k] = ex2(s[k]);
    l0 += (e[0] + e[1]) + (e[4] + e[5]);
    l1 += (e[2] + e[3]) + (e[6] + e[7]);
    pa[0] = pack_bf16(e[0], e[1]); pa[1] = pack_bf16(e[2], e[3]); pa[2] = pack_bf16(e[4], e[5]); pa[3] = pack_bf16(e[6], e[7]);
}
__device__ __forceinline__ void load_q(uint32_t (&q0)[4], uint32_t (&q1)[2], uint32_t qaddr, int c0, int lane, uint32_t mlo, uint32_t mhi) {
    ldsm_x4(q0, qaddr + (c0 + (lane >> 4)) * 2048);
    ldsm_x2(q1[0], q1[1], qaddr + (c0 + 2) * 2048);
    asm volatile("and.b32 %0, %0, %4;\n and.b32 %1, %1, %4;\n and.b32 %2, %2, %5;\n and.b32 %3, %3, %5;"
                 : "+r"(q0[0]), "+r"(q0[1]), "+r"(q1[0]), "+r"(q1[1]) : "r"(mlo), "r"(mhi));
}

__device__ __noinline__ void attn_tile_online(float* res, uint32_t qaddr, int c0, uint32_t mlo, uint32_t mhi, uint32_t kA, uint32_t kB,
                                              uint32_t vA, int key_diag, int key_min, int lane) {
    const int g = lane >> 2, i = lane & 3;
    uint32_t q0[4], q1[2];
    load_q(q0, q1, qaddr, c0, lane, mlo, mhi);
    float o[3][4], l0 = 0.f, l1 = 0.f, m0 = -INFINITY, m1 = -INFINITY;
#pragma unroll
    for (int k = 0; k < 4; k++) o[0][k] = o[1][k] = o[2][k] = 0.f;
    const bool k0 = 2 * i <= g, k1 = 2 * i + 1 <= g;
    const float zero4[4] = {0.f, 0.f, 0.f, 0.f};
#pragma unroll 1
    for (int t = 0; t <= 16; t++) {
        const int key = key_diag - 16 * t;
        if (key < key_min) break;
        KFrag kf;
        float d[8];
        load_k(kf, kA, kB, key_off(key));
        s_mma(d, q0, q1, kf, zero4);
        if (t == 0) {
            if (!k0) d[0] = d[6] = -INFINITY;
            if (!k1) d[1] = d[7] = -INFINITY;
            d[4] = d[5] = -INFINITY;
        } else if (t == 16) {
            if (k0) d[0] = d[6] = -INFINITY;
            if (k1) d[1] = d[7] = -INFINITY;
            d[2] = d[3] = -INFINITY;
        }
        float c0m = fmaxf(fmaxf(d[0], d[1]), fmaxf(d[4], d[5])), c1m = fmaxf(fmaxf(d[2], d[3]), fmaxf(d[6], d[7]));
        c0m = fmaxf(c0m, __shfl_xor_sync(0xffffffffu, c0m, 1));
        c1m = fmaxf(c1m, __shfl_xor_sync(0xffffffffu, c1m, 1));
        c0m = fmaxf(c0m, __shfl_xor_sync(0xffffffffu, c0m, 2));
        c1m = fmaxf(c1m, __shfl_xor_sync(0xffffffffu, c1m, 2));
        const float n0 = fmaxf(m0, c0m), n1 = fmaxf(m1, c1m);
        const float a0 = ex2(m0 - n0), a1 = ex2(m1 - n1);
        m0 = n0; m1 = n1;
#pragma unroll
        for (int k = 0; k < 3; k++) { o[k][0] *= a0; o[k][1] *= a0; o[k][2] *= a1; o[k][3] *= a1; }
        l0 *= a0; l1 *= a1;
#pragma unroll
        for (int k = 0; k < 8; k++) d[k] -= (k & 2) ? m1 : m0;
        uint32_t pa[4];
        exp_block(pa, d, l0, l1);
        load_v(kf, vA, kB, key_off(key));
        pv_mma(o, pa, kf);
    }
    l0 += __shfl_xor_sync(0xffffffffu, l0, 1);
    l1 += __shfl_xor_sync(0xffffffffu, l1, 1);
    l0 += __shfl_xor_sync(0xffffffffu, l0, 2);
    l1 += __shfl_xor_sync(0xffffffffu, l1, 2);
#pragma unroll
    for (int k = 0; k < 12; k++) res[k] = o[k >> 2][k & 3];
    res[12] = l0;
    res[13] = l1;
}

struct UnitDesc { uint32_t kd, vd, lb1; int nv; };
__device__ __forceinline__ void unit_setup(UnitDesc& d, uint32_t (&q0)[4], uint32_t (&q1)[4], uint32_t sb, int rb, int u, int w, int lane) {
    const int hl = u & 3, qh = u >> 2, i = lane & 3;
    const int c0 = 2 * hl, off = 2 * hl;
    const uint32_t qa = sb + P2_Q + (64 * qh + 16 * w + (lane & 7) + ((lane >> 3) & 1) * 8) * 16;
    ldsm_x4(q0, qa + (c0 + (lane >> 4)) * 2048);
    ldsm_x2(q1[0], q1[1], qa + (c0 + 2) * 2048);
    const uint32_t mlo = (2 * i < off) ? 0u : 0xffffffffu, mhi = (16 + 2 * i >= off + 18) ? 0u : 0xffffffffu;
    asm volatile("and.b32 %0, %0, %4;\n and.b32 %1, %1, %4;\n and.b32 %2, %2, %5;\n and.b32 %3, %3, %5;"
                 : "+r"(q0[0]), "+r"(q0[1]), "+r"(q1[0]), "+r"(q1[1]) : "r"(mlo), "r"(mhi));
    q1[2] = q1[3] = 0u;
    const uint32_t kb0 = sb + P2_K + qh * 9216 + c0 * 1024, vb0 = sb + P2_V + qh * 9216 + c0 * 1024;
    d.kd = (kb0 & 0x3FFFF) >> 4;
    d.vd = ((vb0 & 0x3FFFF) >> 4) | (8u << 16);
    d.lb1 = ((sb + ONES_OFF - (kb0 + 2048)) >> 4) << 16;
    d.nv = min(5, (128 * rb + 64 * qh) / 64 + 1);
}
__device__ __forceinline__ void unit_store(const float (&o)[12], float l0, float l1, uint32_t sb, int u, int w, int lane) {
    const int hl = u & 3, qh = u >> 2, g = lane >> 2, i = lane & 3, c0 = 2 * hl, off = 2 * hl;
    const float r0 = __fdividef(1.f, l0), r1 = __fdividef(1.f, l1);
    const uint32_t stg = sb + P2_O + qh * 9216 + c0 * 1024 + (16 * w + g) * 16 + 4 * i;
    const uint32_t a0 = (2 * i >= off) ? stg : (sb + DUMMY_OFF), a2 = (2 * i < off + 2) ? stg + 2048 : (sb + DUMMY_OFF);
    const uint32_t h0 = (2 * i >= off) ? 128 : 0, h2 = (2 * i < off + 2) ? 128 : 0;
    sts32(a0, pack_bf16(o[0] * r0, o[1] * r0));
    sts32(a0 + h0, pack_bf16(o[2] * r1, o[3] * r1));
    sts32(stg + 1024, pack_bf16(o[4] * r0, o[5] * r0));
    sts32(stg + 1024 + 128, pack_bf16(o[6] * r1, o[7] * r1));
    sts32(a2, pack_bf16(o[8] * r0, o[9] * r0));
    sts32(a2 + h2, pack_bf16(o[10] * r1, o[11] * r1));
}
__device__ __forceinline__ bool unit_finish(const float (&o)[12], float l0, float l1, uint32_t sb, int u, int w, int lane) {
    l0 += __shfl_xor_sync(0xffffffffu, l0, 1);
    l1 += __shfl_xor_sync(0xffffffffu, l1, 1);
    l0 += __shfl_xor_sync(0xffffffffu, l0, 2);
    l1 += __shfl_xor_sync(0xffffffffu, l1, 2);
    const float z = (fmaf(o[0], 0.f, o[1] * 0.f) + fmaf(o[2], 0.f, o[3] * 0.f)) + (fmaf(o[4], 0.f, o[5] * 0.f) + fmaf(o[6], 0.f, o[7] * 0.f)) +
                    (fmaf(o[8], 0.f, o[9] * 0.f) + fmaf(o[10], 0.f, o[11] * 0.f));
    const bool bad = !(fmaxf(l0, l1) + z <= 1.0e17f) || !(l0 == l0) || !(l1 == l1);
    unit_store(o, l0, l1, sb, u, w, lane);
    return __any_sync(0xffffffffu, bad);
}
__device__ __forceinline__ void unit_redo(uint32_t sb, int rb, int u, int w, int lane) {
    const int hl = u & 3, qh = u >> 2, i = lane & 3, c0 = 2 * hl, off = 2 * hl;
    float res[14], o[12];
    const int row = 64 * qh + 16 * w;
    const uint32_t mlo = (2 * i < off) ? 0u : 0xffffffffu, mhi = (16 + 2 * i >= off + 18) ? 0u : 0xffffffffu;
    const uint32_t kA = sb + P2_K + c0 * 1024 + ((lane & 7) + (lane >> 4) * 8) * 16 + ((lane >> 3) & 1) * 1024;
    const uint32_t kB = sb + P2_K + c0 * 1024 + (lane & 15) * 16 + 2048;
    const uint32_t vA = sb + P2_V + c0 * 1024 + (lane & 15) * 16 + (lane >> 4) * 1024;
    attn_tile_online(res, sb + P2_Q + (row + (lane & 7) + ((lane >> 3) & 1) * 8) * 16, c0, mlo, mhi, kA, kB, vA, 256 + row,
                     max(256 - 128 * rb, row), lane);
#pragma unroll
    for (int k = 0; k < 12; k++) o[k] = res[k];
    unit_store(o, res[12], res[13], sb, u, w, lane);
}
__device__ __forceinline__ void ex2_all(float (&s)[32]) {
#pragma unroll
    for (int k = 0; k < 32; k++) s[k] = ex2(s[k]);
}
__device__ __forceinline__ void sum_pack(const float (&s)[32], uint32_t (&pp)[4][4], bool ok, float& l0, float& l1) {
    float a0 = 0.f, a1 = 0.f;
#pragma unroll
    for (int k = 0; k < 4; k++) {
        a0 += (s[8 * k] + s[8 * k + 1]) + (s[8 * k + 4] + s[8 * k + 5]);
        a1 += (s[8 * k + 2] + s[8 * k + 3]) + (s[8 * k + 6] + s[8 * k + 7]);
        pp[k][0] = pack_bf16(s[8 * k], s[8 * k + 1]);
        pp[k][1] = pack_bf16(s[8 * k + 2], s[8 * k + 3]);
        pp[k][2] = pack_bf16(s[8 * k + 4], s[8 * k + 5]);
        pp[k][3] = pack_bf16(s[8 * k + 6], s[8 * k + 7]);
    }
    l0 += ok ? a0 : 0.f;
    l1 += ok ? a1 : 0.f;
}

__device__ __forceinline__ void attn_units(const Params& p, uint32_t sb, int c, int wg, int tid) {
    const uint32_t bars = sb + BAR_OFF;
    const int rb = p2_rb(c);
    const int lane = tid & 31, w = __shfl_sync(0xffffffffu, (tid >> 5) & 3, 0), g = lane >> 2, i = lane & 3;
    const bool k0 = 2 * i <= g, k1 = 2 * i + 1 <= g;
    unsigned* ctr = reinterpret_cast<unsigned*>(__cvta_shared_to_generic(sb + UNIT_CTR));
    const uint32_t slot = sb + UNIT_CTR + 4 + 8 * wg;
    const bool dry = c >= 128;
    if ((tid & 127) == 0) sts32(slot, atomicAdd(ctr, 1u));
    if (!dry) mbar_wait(bars + 8 * B_KV, 0);
    TSTAMP_IF(tid == 0, 6);
    bar_sync(2 + wg, 128);
    int u = __shfl_sync(0xffffffffu, (int)lds32(slot), 0);
    if (u < 8) {
        float sA[32], o[12], l0 = 0.f, l1 = 0.f;
        uint32_t q0[4], q1[4], pp[4][4];
        UnitDesc d;
        unit_setup(d, q0, q1, sb, rb, u, w, lane);
        wg_fence();
        wg_S(sA, q0, q1, d.kd, d.lb1, 4);
        wg_commit();
        int uprev = -1, par = 1;
        uint32_t redo = 0;
        int round = 0;
        (void)round;
#pragma unroll 1
        while (true) {
            if ((tid & 127) == 0) sts32(slot + 4 * par, atomicAdd(ctr, 1u));
            wg_wait<0>();
            pin(sA);
            pin(o);
            FSTAMP(0);
            float ot[12];
#pragma unroll
            for (int k = 0; k < 12; k++) asm volatile("mov.f32 %0, %1;" : "=f"(ot[k]) : "f"(o[k]));
            const float lp0 = l0, lp1 = l1;
            l0 = l1 = 0.f;
            {
                uint32_t nm;
                if (w == 0) diag_chunk<0>(sA, pp, k0, k1, l0, l1, nm);
                else if (w == 1) diag_chunk<1>(sA, pp, k0, k1, l0, l1, nm);
                else if (w == 2) diag_chunk<2>(sA, pp, k0, k1, l0, l1, nm);
                else diag_chunk<3>(sA, pp, k0, k1, l0, l1, nm);
                q1[2] = (i == 0) ? (nm & 0xffffu) : 0u;
                q1[3] = (i == 0) ? (nm >> 16) : 0u;
            }
            if (uprev < 0 && !dry) mbar_wait(bars + 8 * (B_KV + 1), 0);
            FSTAMP(1);
            wg_fence();
            wg_S(sA, q0, q1, d.kd, d.lb1, 3); wg_commit();
            wg_PV<1>(o, pp, d.vd, 4); wg_commit();
            if (uprev >= 0) redo |= (unit_finish(ot, lp0, lp1, sb, uprev, w, lane) ? 1u : 0u) << uprev;
            else if (!dry) {
                mbar_wait(bars + 8 * (B_KV + 2), 0);
                mbar_wait(bars + 8 * (B_KV + 3), 0);
                TSTAMP_IF(tid == 0, 7);
            }
            bar_sync(2 + wg, 128);
            const int un = __shfl_sync(0xffffffffu, (int)lds32(slot + 4 * par), 0);
            par ^= 1;
            FSTAMP(2);
            const int jmin = max(1, 5 - d.nv);
#pragma unroll 1
            for (int j = 3; j >= jmin; j--) {
                wg_wait<0>();
                pin(sA);
                ex2_all(sA);
                sum_pack(sA, pp, (4 - j) < d.nv, l0, l1);
                wg_fence();
                wg_S(sA, q0, q1, d.kd, d.lb1, j - 1); wg_commit();
                wg_PV<0>(o, pp, d.vd, j); wg_commit();
            }
            FSTAMP(3);
            wg_wait<0>(); pin(sA);
            const uint32_t vd0 = d.vd;
            const bool edge_ok = d.nv == 5;
            if (un < 8) unit_setup(d, q0, q1, sb, rb, un, w, lane);
            wg_wait<0>();
            {
                float a0 = 0.f, a1 = 0.f;
                if (w == 0) edge_chunk<0>(sA, pp, k0, k1, a0, a1);
                else if (w == 1) edge_chunk<1>(sA, pp, k0, k1, a0, a1);
                else if (w == 2) edge_chunk<2>(sA, pp, k0, k1, a0, a1);
                else edge_chunk<3>(sA, pp, k0, k1, a0, a1);
                l0 += edge_ok ? a0 : 0.f;
                l1 += edge_ok ? a1 : 0.f;
            }
            FSTAMP(4);
            wg_fence();
            wg_PV<0>(o, pp, vd0, 0);
            wg_S(sA, q0, q1, d.kd, d.lb1, 4);
            wg_commit();
            uprev = u;
            u = un;
            round++;
            if (u >= 8) break;
        }
        wg_wait<0>();
        pin(o);
        pin(sA);
        redo |= (unit_finish(o, l0, l1, sb, uprev, w, lane) ? 1u : 0u) << uprev;
#pragma unroll 1
        while (redo) {
            const int ur = __ffs(redo) - 1;
            redo &= redo - 1;
            unit_redo(sb, rb, ur, w, lane);
        }
    }
    fence_async_smem();
    __syncwarp();
    if (lane == 0) mbar_arrive(bars + 8 * B_ODONE);
    TSTAMP_IF(tid == 0, 8);
}
__device__ __forceinline__ void phase2_start(const Params& p, uint32_t sb, int c, int tid) {
    if (tid == 0) {
        if ((p.mode & M_P1) && c < T_CTAS) mbar_wait(sb + BAR_OFF + 8 * B_XFREE1, 0);
        p2_loads(p, sb, c);
    }
    __syncwarp();
}
__device__ __forceinline__ void phase2_finish(const Params& p, uint32_t sb, int c, int tid) {
    const uint32_t bars = sb + BAR_OFF;
    if (tid == 0 || tid == 128) {
        const int hg = p2_hg(c), rb = p2_rb(c);
        const int qh = tid >> 7, q0w = 128 * rb + 64 * qh;
        mbar_wait(bars + 8 * B_ODONE, 0);
        tma_store2d(&p.mOst, 2 * q0w, 9 * hg, sb + P2_O + qh * 9216);
        bulk_commit();
        bulk_wait0();
        if (p.mode & M_FUSED) signal_add(CNT_P2 + q0w / 64);
        mbar_arrive(bars + 8 * B_XFREE2);
        TSTAMP_IF(tid == 0, 9);
        TSTAMP_IF(tid == 128, 15);
    }
    __syncwarp();
}

__device__ __forceinline__ void phase3(const Params& p, uint32_t sb, int c, int wg, int tid) {
    const uint32_t bars = sb + BAR_OFF;
    const int dt = c % 9, nt = c / 9, t0 = nt * TROWS;
    if (tid >= 256 && tid < 288) {
        if (tid == 256) {
            if (p.mode & M_P2) mbar_wait(bars + 8 * B_XFREE2, 0);
            else if (p.mode & M_P1) mbar_wait(bars + 8 * B_XFREE1, 0);
            for (int kb = 0; kb < P3_STAGES; kb++) p3_load_w(p, sb, dt, kb);
            if (p.mode & M_FUSED) {
                const int r1 = min(t0 + TROWS - 1, SEQ - 1);
                wait_counters(CNT_P2 + t0 / 64, r1 / 64 - t0 / 64 + 1, 8);
            }
            TSTAMP(10);
            for (int kb = 0; kb < P3_STAGES; kb++) p3_load_o(p, sb, t0, kb);
            for (int kb = P3_STAGES; kb < 9; kb++) {
                mbar_wait(bars + 8 * (B_P3_EMPTY + kb % P3_STAGES), (kb / P3_STAGES - 1) & 1);
                p3_load_w(p, sb, dt, kb);
                p3_load_o(p, sb, t0, kb);
            }
        }
        return;
    }
    const int lane = tid & 31, w = (tid >> 5) & 3, g = lane >> 2, i = lane & 3;
    const bool real = wg < 2;
    float acc[40];
    if (real) {
        const uint64_t da0 = make_desc(sb, 1024, 1024, 1), db0 = make_desc(sb + 8192 + wg * 1280, 2560, 128, 0);
#pragma unroll
        for (int kb = 0; kb < 9; kb++) {
            const int s = kb % P3_STAGES;
            mbar_wait(bars + 8 * (B_P3_FULL + s), (kb / P3_STAGES) & 1);

            wg_fence();
#pragma unroll
            for (int k = 0; k < 4; k++)
                wgmma_ss_n80_t10(acc, da0 + (s * (P3_STAGE >> 4) + k * 128), db0 + (s * (P3_STAGE >> 4) + k * 320), (kb | k) != 0);
            wg_commit();
            if (kb > 0 && kb - 1 + P3_STAGES < 9) {
                wg_wait<1>();
                if (tid % 128 == 0) mbar_arrive(bars + 8 * (B_P3_EMPTY + (kb - 1) % P3_STAGES));
            }
        }
        wg_wait<0>();
        pin(acc);
        TSTAMP_IF(tid == 0, 11);
        mbar_wait(bars + 8 * B_P3_Z, 0);
        TSTAMP_IF(tid == 0, 12);
    } else {
#pragma unroll
        for (int k = 0; k < 40; k++) acc[k] = 0.f;
    }
    const int tl0 = real ? wg * 80 : 0;
    const uint32_t one2 = 0x3f803f80u;
    uint32_t xf[10][2], zf[10][2], gf[10];
    const int rsw = lane & 7;
    const uint32_t xa0 = sb + P3_X + (tl0 + rsw) * 128 + (((2 * w + ((lane >> 3) & 1)) ^ rsw) << 4);
    const uint32_t za0 = sb + P3_Z + (16 * w + g) * (TROWS * 2) + (tl0 + 2 * i) * 2;
#pragma unroll
    for (int j = 0; j < 10; j++) {
        ldsm_x2_t(xf[j][0], xf[j][1], xa0 + j * 1024);
        zf[j][0] = lds32(za0 + j * 16);
        zf[j][1] = lds32(za0 + j * 16 + 8 * TROWS * 2);
        gf[j] = lds32(sb + GATE_OFF + (tl0 + 8 * j + 2 * i) * 2);
    }
    TSTAMP_IF(tid == 0, 25);
    const uint32_t dump = sb + DUMMY_OFF + (lane & 7) * 16;
#pragma unroll
    for (int j = 0; j < 10; j++) {
        const uint32_t og = hsub2(one2, gf[j]);
        const uint32_t r0 = hadd2(hmul2(gf[j], hmul2(xf[j][0], zf[j][0])), hmul2(og, pack_bf16(acc[4 * j], acc[4 * j + 1])));
        const uint32_t r1 = hadd2(hmul2(gf[j], hmul2(xf[j][1], zf[j][1])), hmul2(og, pack_bf16(acc[4 * j + 2], acc[4 * j + 3])));
        stsm_x2_t((real && (j < 9 || wg == 0)) ? xa0 + j * 1024 : dump, r0, r1);
    }
    if (!real) return;
    TSTAMP_IF(tid == 0, 26);
    fence_async_smem();
    bar_sync(1, 256);
    if (tid == 0) {
        TSTAMP(13);
        tma_store2d(&p.mOut, dt * 64, nt * TROWS, sb + P3_X);
        bulk_commit();
        bulk_wait0();
        TSTAMP(14);
    }
}

__device__ __forceinline__ void prepass(const Params& p, uint32_t sb, int c, int tid) {
    const uint32_t bars = sb + BAR_OFF;
    const int lane = tid & 31, wq = (tid >> 5) & 3, i = lane & 3;
    const int dt = c % 9, nt = c / 9;
    const int t0 = nt * TROWS, d0 = dt * 64;
    if (tid % 128 == 0) {
        if (c < T_CTAS) {
            mbar_expect(bars + 8 * B_PRE, 20480 + 19456);
            tma_load2d(sb + PRE_K, &p.mK160, d0, t0 - 8, bars + 8 * B_PRE);
            tma_load2d(sb + PRE_V, &p.mV152, d0, t0, bars + 8 * B_PRE);
        }
    }
    if (c < T_CTAS) {
        uint32_t wt[2][4];
#pragma unroll
        for (int ss = 0; ss < 2; ss++) {
            const int ch = d0 + 8 * (2 * wq + ss) + 2 * i;
            const uint4 v = __ldg(reinterpret_cast<const uint4*>(p.shift_k + ch * 4));
            wt[ss][0] = __byte_perm(v.x, v.z, 0x5410);
            wt[ss][1] = __byte_perm(v.x, v.z, 0x7632);
            wt[ss][2] = __byte_perm(v.y, v.w, 0x5410);
            wt[ss][3] = __byte_perm(v.y, v.w, 0x7632);
        }
        mbar_wait(bars + 8 * B_PRE, 0);
        TSTAMP_IF(tid == 384, 16);
        if (tid % 128 == 0) {
            l2_prefetch(reinterpret_cast<const char*>(p.wo) + (size_t)c * 5264, (c == T_CTAS - 1) ? (576 * 576 * 2 - 125 * 5264) : 5264);
        }
        uint32_t kk[2][2][5][4];
        auto load_group = [&](int G, uint32_t (&dst)[2][5][4]) {
            const int B = 4 * G + (lane >> 3);
            const int tl = min(8 * B + 7 - (lane & 7), 151);
#pragma unroll
            for (int ss = 0; ss < 2; ss++) {
                const int strip = 2 * wq + ss;
#pragma unroll
                for (int jt = 0; jt < 4; jt++) {
                    const int row = tl + 8 - jt;
                    ldsm_x4(dst[ss][jt], sb + PRE_K + row * 128 + ((strip ^ (row & 7)) << 4));
                }
                ldsm_x4(dst[ss][4], sb + PRE_V + tl * 128 + ((strip ^ (tl & 7)) << 4));
            }
        };
        load_group(0, kk[0]);
#pragma unroll
        for (int G = 0; G < 5; G++) {
            if (G < 4) load_group(G + 1, kk[(G + 1) & 1]);
            const int B = 4 * G + (lane >> 3);
#pragma unroll
            for (int ss = 0; ss < 2; ss++) {
                const uint32_t (&f)[5][4] = kk[G & 1][ss];
                uint32_t r[4];
#pragma unroll
                for (int m = 0; m < 4; m++) {
                    uint32_t a = hmul2(f[3][m], wt[ss][3]);
                    a = hadd2(a, hmul2(f[2][m], wt[ss][2]));
                    a = hadd2(a, hmul2(f[1][m], wt[ss][1]));
                    a = hadd2(a, hmul2(f[0][m], wt[ss][0]));
                    r[m] = hmul2(a, f[4][m]);
                }
                const uint32_t dst = (B < 19) ? (sb + PRE_ST + (8 * (2 * wq + ss) + (lane & 7)) * (TROWS * 2) + (18 - B) * 16)
                                              : (sb + DUMMY_OFF + (lane & 7) * 16);
                stsm_x4_t(dst, r[0], r[1], r[2], r[3]);
            }
        }
        fence_async_smem();
        bar_sync(5, 128);
        if (tid % 128 == 0) {
            tma_store2d(&p.mKvR, 128 + SEQ - t0 - TROWS, d0, sb + PRE_ST);
            bulk_commit();
        }
    }
    if (c < T_CTAS && tid % 128 == 0) {
        bulk_wait0();
        if (p.mode & M_FUSED) signal_add(CNT_PRE + dt);
        TSTAMP(17);
    }
    fence_async_smem();
    bar_sync(5, 128);
}

__device__ __forceinline__ void gate_rows(const Params& p, uint32_t sb, int c, int tid) {
    const int lane = tid & 31, wq = (tid >> 5) & 3;
    uint4 xa[4][3], gw[3];
#pragma unroll
    for (int k = 0; k < 3; k++) {
        const int ck = min(lane + 32 * k, 71);
        gw[k] = __ldg(reinterpret_cast<const uint4*>(p.gate_w + ck * 8));
#pragma unroll
        for (int r = 0; r < 4; r++) xa[r][k] = __ldg(reinterpret_cast<const uint4*>(p.x + (size_t)(16 * c + 4 * wq + r) * DM + ck * 8));
    }
    float mine = 0.f;
#pragma unroll
    for (int r = 0; r < 4; r++) {
        float s = 0.f;
#pragma unroll
        for (int k = 0; k < 3; k++) {
            float q = 0.f;
            uint32_t m;
            m = hmul2(xa[r][k].x, gw[k].x); q += bf_lo(m) + bf_hi(m);
            m = hmul2(xa[r][k].y, gw[k].y); q += bf_lo(m) + bf_hi(m);
            m = hmul2(xa[r][k].z, gw[k].z); q += bf_lo(m) + bf_hi(m);
            m = hmul2(xa[r][k].w, gw[k].w); q += bf_lo(m) + bf_hi(m);
            if (lane + 32 * k < 72) s += q;
        }
#pragma unroll
        for (int o = 16; o > 0; o >>= 1) s += __shfl_xor_sync(0xffffffffu, s, o);
        if (lane == r) mine = s;
    }
    const uint32_t stg = sb + GSTG_OFF;
    if (lane < 4) {
        const bf16 gv = __float2bfloat16_rn(1.f / (1.f + __expf(-rbf(mine))));
        asm volatile("st.shared.u16 [%0], %1;" ::"r"(stg + (4 * wq + lane) * 2), "h"(*reinterpret_cast<const unsigned short*>(&gv)) : "memory");
    }
    fence_async_smem();
    bar_sync(3, 128);
    if (tid == 128) {
        bulk_store(reinterpret_cast<bf16*>(g_gate) + 16 * c, stg, 32);
        bulk_commit();
        bulk_wait0();
        if (p.mode & M_FUSED) signal_add(CNT_G);
        TSTAMP(18);
    }
    __syncwarp();
}

__device__ __forceinline__ void conv_load_filter(const Params& p, uint32_t slot, uint32_t bar, int ch) {
    mbar_expect(bar, 4096);
    bulk_load(slot + C_E + 16, p.ssm_k + (size_t)ch * SEQ, 4096, bar);
}
__device__ __forceinline__ void conv_load_data(uint32_t slot, uint32_t bar, int ch) {
    mbar_expect(bar, 4096);
    bulk_load(slot, g_kvR + (size_t)ch * KVR_PITCH + 128, 4096, bar);
}
__device__ __forceinline__ void conv_zero_pads(uint32_t slot, int lane) {
    if (lane < 16) sts128(slot + 4096 + lane * 16, 0u, 0u, 0u, 0u);
    else if (lane == 16) sts128(slot + C_E, 0u, 0u, 0u, 0u);
    else if (lane == 17) sts128(slot + C_E + 4112, 0u, 0u, 0u, 0u);
}
template <int KSTEP>
__device__ __forceinline__ void conv_build_o(uint32_t slot, int lane, int k0) {
    constexpr int NK = (9 + KSTEP - 1) / KSTEP;
    uint32_t a[NK][5];
#pragma unroll
    for (int n = 0; n < NK; n++) {
        const int w0 = min(((k0 + n * KSTEP) * 32 + lane) * 4, 1024);
        asm volatile("ld.shared.v4.u32 {%0,%1,%2,%3}, [%4];" : "=r"(a[n][0]), "=r"(a[n][1]), "=r"(a[n][2]), "=r"(a[n][3])
                     : "r"(slot + C_E + w0 * 4) : "memory");
        a[n][4] = lds32(slot + C_E + w0 * 4 + 16);
    }
#pragma unroll
    for (int n = 0; n < NK; n++) {
        const int w0 = min(((k0 + n * KSTEP) * 32 + lane) * 4, 1024);
        sts128(slot + C_O + w0 * 4, __byte_perm(a[n][0], a[n][1], 0x5432), __byte_perm(a[n][1], a[n][2], 0x5432),
               __byte_perm(a[n][2], a[n][3], 0x5432), __byte_perm(a[n][3], a[n][4], 0x5432));
    }
}
template <int NQ>
__device__ __forceinline__ void conv_stage_z(uint32_t slot, int q0, const float (&y)[NQ][4], uint32_t d2, int lane) {
    uint32_t kvr[NQ][2];
#pragma unroll
    for (int q = 0; q < NQ; q++) {
        kvr[q][0] = lds32(slot + (1023 - (64 * (q0 + q) + lane)) * 4);
        kvr[q][1] = lds32(slot + (1023 - (64 * (q0 + q) + 32 + lane)) * 4);
    }
#pragma unroll
    for (int q = 0; q < NQ; q++) {
#pragma unroll
        for (int h = 0; h < 2; h++) {
            const uint32_t kvp = __byte_perm(kvr[q][h], kvr[q][h], 0x1032);
            sts32(slot + C_E + (64 * (q0 + q) + 32 * h + lane) * 4, hadd2(pack_bf16(y[q][2 * h], y[q][2 * h + 1]), hmul2(kvp, d2)));
        }
    }
}
__device__ __forceinline__ void conv_store_z(const Params& p, uint32_t slot, int ch) {
    bulk_store(g_zT + (size_t)ch * SEQ, slot + C_E, 4096);
    bulk_commit();
    bulk_wait0();
    if (p.mode & M_FUSED) signal_add(CNT_Z + ch / 64);
}

__device__ __forceinline__ void conv_finish_z(const Params& p, int c, int tid) {
    const int wid = tid >> 5;
    if (c >= 128 && wid >= 8) return;
    if ((tid & 31) == 0) {
        bulk_wait0();
        if (p.mode & M_FUSED) signal_add(CNT_Z + ((c < 128) ? (4 * c + (wid & 3)) : (512 + 8 * (c - 128) + wid)) / 64);
    }
    __syncwarp();
}

template <int job0>
__device__ __forceinline__ void conv_task(const Params& p, uint32_t sb, int c, int tid) {
    const int lane = tid & 31, wid = tid >> 5, wq = wid & 3, g = lane >> 2, i = lane & 3;
    if (c >= 128 && wid >= 8) return;
    const int ch = (c < 128) ? (4 * c + wq) : (512 + 8 * (c - 128) + wid);
    const uint32_t slot0 = (c < 128) ? (sb + C_OFF + wq * C_SLOT) : (sb + wid * C_SLOT);
    const uint32_t bar0 = sb + BAR_OFF + 8 * ((c < 128) ? (B_CONV + wq) : wid);
    int ch5 = 0;
    if (job0 == 1) {
        if (c >= 128) return;
        const uint32_t xslot = sb + UNIT_CTR + 40;
        if (tid == 384) sts32(xslot, (p.mode & M_FUSED) ? atomicAdd(&g_cnt[CNT_EXTRA * CNT_STRIDE], 1u) : ((c & 15) < 4 ? (c >> 4) * 4 + (c & 15) : 32u));
        bar_sync(5, 128);
        const int e = (int)lds32(xslot);
        if (e >= 32) return;
        ch5 = 544 + e;
    }
    const uint32_t bard0 = sb + BAR_OFF + 8 * ((c < 128) ? (B_CONVD + wq) : (8 + wid));
    const uint32_t slot5 = sb + C_OFF + 4 * C_SLOT, bar5 = sb + BAR_OFF + 8 * (B_CONV + 4), bard5 = sb + BAR_OFF + 8 * (B_CONVD + 4);
    if (job0 == 0) {
        if (lane == 0) conv_load_filter(p, slot0, bar0, ch);
        if (lane == 0 && wq == 0 && (c < 128 || wid == 0)) {
            if (p.mode & M_FUSED) wait_counter(CNT_PRE + ch / 64, 14);
            const int nw = (c < 128) ? 4 : 8;
            for (int k = 0; k < nw; k++)
                conv_load_data(slot0 + k * C_SLOT, bard0 + 8 * k, ch + k);
        }
        TSTAMP_IF(tid == 384, 19);
        conv_zero_pads(slot0, lane);
        mbar_wait(bar0, 0);
        __syncwarp();
        conv_build_o<1>(slot0, lane, 0);
        TSTAMP_IF(tid == 384, 21);
        mbar_wait(bard0, 0);
        TSTAMP_IF(tid == 384, 20);
        __syncwarp();
    }
    {
        const int job = job0;
        if (job == 1) {
            if (tid == 384) {
                if (p.mode & M_FUSED) wait_counter(CNT_PRE + 8, 14);
                conv_load_filter(p, slot5, bar5, ch5);
                conv_load_data(slot5, bard5, ch5);
            }
            if (wq == 1) conv_zero_pads(slot5, lane);
        }
        const uint32_t slot = job ? slot5 : slot0;
        if (job) {
            bar_sync(5, 128);
            mbar_wait(bar5, 0);
            mbar_wait(bard5, 0);
            conv_build_o<4>(slot5, lane, wq);
            bar_sync(5, 128);
        }
        float acc[16][4];
#pragma unroll
        for (int q = 0; q < 16; q++) acc[q][0] = acc[q][1] = acc[q][2] = acc[q][3] = 0.f;
        const uint32_t baddr0 = slot + ((g & 1) ? C_E : C_O) + (((g + 1) >> 1) + i) * 4;
        const int ar = (lane & 7) + ((lane >> 3) & 1) * 8, ak = (lane >> 4) * 8;
        const uint32_t aaddr0 = slot + (2040 - 8 * ar + ak) * 2;
        const int rho0 = job ? 4 * wq : 0, rho1 = job ? 4 * wq + 4 : 16;
        uint32_t bb[16][2], a[2][4];
        ldsm_x4(a[0], aaddr0 + rho0 * 16);
#pragma unroll
        for (int ii = 0; ii < 16; ii++) {
            bb[ii][0] = lds32(baddr0 + (16 * ii + rho0) * 16);
            bb[ii][1] = lds32(baddr0 + (16 * ii + rho0 + 1) * 16);
        }
        uint32_t ap = aaddr0 + rho0 * 16, bp = baddr0 + (rho0 + 2) * 16;
#pragma unroll 1
        for (int n = (rho1 - rho0) >> 1; n > 0; n--) {
#pragma unroll
            for (int x = 0; x < 16; x++) {
                if (x < 15) ldsm_x4(a[(x + 1) & 1], ap - 256 * (x + 1));
                else ldsm_x4(a[0], ap + 32);
#pragma unroll
                for (int ii = 0; ii + x < 16; ii++) mma16816v(acc[x + ii], a[x & 1], bb[ii][0], bb[ii][1]);
                bb[15 - x][0] = lds32(bp + 256 * (15 - x));
                bb[15 - x][1] = lds32(bp + 256 * (15 - x) + 16);
                __syncwarp();
            }
            ap += 32;
            bp += 32;
        }
        TSTAMP_IF(tid == 384 && job == 0, 22);
        const int chj = job ? ch5 : ch;
        const float dcoef = __bfloat162float(p.ssm_D[chj]);
        const uint32_t d2 = pack_bf16(dcoef, dcoef);
        __syncwarp();
        if (job == 0) {
            conv_stage_z<16>(slot, 0, acc, d2, lane);
            fence_async_smem();
            __syncwarp();
            if (lane == 0) {
                bulk_store(g_zT + (size_t)ch * SEQ, slot + C_E, 4096);
                bulk_commit();
            }
            __syncwarp();
        } else {
#pragma unroll
            for (int q = 0; q < 16; q++)
                sts128(slot0 + q * 512 + lane * 16, __float_as_uint(acc[q][0]), __float_as_uint(acc[q][1]), __float_as_uint(acc[q][2]),
                       __float_as_uint(acc[q][3]));
            bar_sync(5, 128);
            float y[4][4];
#pragma unroll
            for (int qq = 0; qq < 4; qq++) {
                y[qq][0] = y[qq][1] = y[qq][2] = y[qq][3] = 0.f;
#pragma unroll
                for (int k = 0; k < 4; k++) {
                    uint32_t a0, a1, a2, a3;
                    asm volatile("ld.shared.v4.u32 {%0,%1,%2,%3}, [%4];" : "=r"(a0), "=r"(a1), "=r"(a2), "=r"(a3)
                                 : "r"(sb + C_OFF + k * C_SLOT + (4 * wq + qq) * 512 + lane * 16) : "memory");
                    y[qq][0] += __uint_as_float(a0); y[qq][1] += __uint_as_float(a1); y[qq][2] += __uint_as_float(a2); y[qq][3] += __uint_as_float(a3);
                }
            }
            conv_stage_z<4>(slot, 4 * wq, y, d2, lane);
            fence_async_smem();
            bar_sync(5, 128);
            if (tid == 384) conv_store_z(p, slot, ch5);
            __syncwarp();
        }
    }
    fence_async_smem();
}

__device__ __forceinline__ void p3_epilogue_loads(const Params& p, uint32_t sb, int c, int tid) {
    bar_sync(5, 128);
    if (tid == 384) {
        const int dt = c % 9, nt = c / 9, t0 = nt * TROWS;
        const int nrows = min(TROWS, SEQ - t0);
        const uint32_t bar = sb + BAR_OFF + 8 * B_P3_Z;
        mbar_expect(bar, 2 * 64 * TROWS * 2 + nrows * 2);
        tma_load2d(sb + P3_X, &p.mX152, dt * 64, t0, bar);
        if (p.mode & M_FUSED) {
            wait_counter(CNT_Z + dt, 64);
            wait_counter(CNT_G, 128);
        }
        TSTAMP(24);
        tma_load2d(sb + P3_Z, &p.mZ, t0, dt * 64, bar);
        bulk_load(sb + GATE_OFF, reinterpret_cast<const bf16*>(g_gate) + t0, nrows * 2, bar);
    }
    __syncwarp();
}

__device__ __forceinline__ void exit_protocol() {
    const unsigned n = atomicAdd(&g_cnt[CNT_EXIT * CNT_STRIDE], 1u);
    if (n == 128 * 6 + 4 * 16 - 1) {
        for (int k = 0; k < CNT_TOTAL; k++) g_cnt[k * CNT_STRIDE] = 0u;
    }
}

__global__ void __launch_bounds__(NTHREADS, 1) gated_mix_kernel(const __grid_constant__ Params p) {
    extern __shared__ uint8_t smem_raw[];
    const uint32_t sb = (smem_u32(smem_raw) + 1023u) & ~1023u;
    const int tid = threadIdx.x, c = blockIdx.x;
    const int wg = __shfl_sync(0xffffffffu, tid >> 7, 0);
    if (tid == 0) {
        const uint32_t bars = sb + BAR_OFF;
#pragma unroll
        for (int k = 0; k < 3; k++) mbar_init(bars + 8 * (B_P1_FULL + k), 1);
        asm volatile("fence.mbarrier_init.release.cluster;" ::: "memory");
        if ((p.mode & M_P1) && c < T_CTAS) {
            for (int kb = 0; kb < P1_STAGES; kb++) p1_load(p, sb, p1_mt(c), p1_nt(c), kb);
        }
#pragma unroll
        for (int k = 3; k < B_COUNT; k++) {
            const int cnt = (k >= B_ODONE) ? 16 : (k == B_XFREE1) ? 3 : (k >= B_P1_EMPTY && k < B_P1_EMPTY + 3) ? (MCAST ? 5 : 2) : (k == B_XFREE2 || (k >= B_P3_EMPTY && k < B_P3_EMPTY + P3_STAGES)) ? 2 : 1;
            mbar_init(bars + 8 * k, c < 128 ? cnt : 1);
        }
        sts32(sb + UNIT_CTR, c < 128 ? 0u : 6u);
        asm volatile("fence.mbarrier_init.release.cluster;" ::: "memory");
    } else if (tid >= 32 && tid < 96) {
        sts128(sb + ONES_OFF + (tid - 32) * 16, 0x00003f80u, 0u, 0u, 0u);
        fence_async_smem();
    } else if (tid == 96) {
        prefetch_tmap(&p.mK160); prefetch_tmap(&p.mV152); prefetch_tmap(&p.mKvR); prefetch_tmap(&p.mQ); prefetch_tmap(&p.mKV);
        prefetch_tmap(&p.mOst); prefetch_tmap(&p.mWo); prefetch_tmap(&p.mOld); prefetch_tmap(&p.mZ); prefetch_tmap(&p.mOut);
    }
    __syncthreads();
    const bool conv_side = (wg == 3 || c >= 128);
    if (wg == 3 || (c >= 128 && wg < 2)) {
        if ((p.mode & M_PRE) && wg == 3) prepass(p, sb, c, tid);
    } else {
        if ((p.mode & M_P1) && (c < T_CTAS || (DRY_L2 && c >= 128))) phase1(p, sb, c, wg, tid);
        if (c < 128) {
            if (p.mode & M_P2) phase2_start(p, sb, c, tid);
            if ((p.mode & M_FUSED) && tid == 0) exit_protocol();
            if ((p.mode & M_PRE) && wg == 1) gate_rows(p, sb, c, tid);
        }
    }
    if (conv_side && (p.mode & M_CONV)) conv_task<0>(p, sb, c, tid);
    TSTAMP_IF(tid == 384, 23);
    if ((p.mode & M_P2) && (c < 128 || (DRY_L2 && wg == 3))) attn_units(p, sb, c, wg, tid);
    if (conv_side && (p.mode & M_CONV)) {
        conv_finish_z(p, c, tid);
        conv_task<1>(p, sb, c, tid);
    }
    if (conv_side) {
        if ((p.mode & M_P3) && c < T_CTAS) p3_epilogue_loads(p, sb, c, tid);
        if ((p.mode & M_FUSED) && (tid & 31) == 0) exit_protocol();
    } else {
        if (p.mode & M_P2) phase2_finish(p, sb, c, tid);
        if ((p.mode & M_P3) && c < T_CTAS) phase3(p, sb, c, wg, tid);
        if ((p.mode & M_FUSED) && tid == 256) exit_protocol();
    }
}

typedef CUresult (*EncodeFn)(CUtensorMap*, CUtensorMapDataType, cuuint32_t, void*, const cuuint64_t*, const cuuint64_t*,
                             const cuuint32_t*, const cuuint32_t*, CUtensorMapInterleave, CUtensorMapSwizzle,
                             CUtensorMapL2promotion, CUtensorMapFloatOOBfill);

static void make_map(EncodeFn enc, CUtensorMap* m, CUtensorMapDataType dt, int esize, const void* base, uint64_t d0, uint64_t d1,
                     uint32_t b0, uint32_t b1, CUtensorMapSwizzle sw) {
    cuuint64_t gd[2] = {d0, d1};
    cuuint64_t gs[1] = {d0 * (uint64_t)esize};
    cuuint32_t bx[2] = {b0, b1};
    cuuint32_t es[2] = {1, 1};
    CUresult r = enc(m, dt, 2, const_cast<void*>(base), gd, gs, bx, es, CU_TENSOR_MAP_INTERLEAVE_NONE, sw,
                     CU_TENSOR_MAP_L2_PROMOTION_L2_128B, CU_TENSOR_MAP_FLOAT_OOB_FILL_NONE);
    (void)r;
}

static void make_map3(EncodeFn enc, CUtensorMap* m, CUtensorMapDataType dt, const void* base, uint64_t d0, uint64_t d1, uint64_t d2,
                      uint64_t s1, uint64_t s2, uint32_t b0, uint32_t b1, uint32_t b2, CUtensorMapSwizzle sw) {
    cuuint64_t gd[3] = {d0, d1, d2};
    cuuint64_t gs[2] = {s1, s2};
    cuuint32_t bx[3] = {b0, b1, b2};
    cuuint32_t es[3] = {1, 1, 1};
    CUresult r = enc(m, dt, 3, const_cast<void*>(base), gd, gs, bx, es, CU_TENSOR_MAP_INTERLEAVE_NONE, sw,
                     CU_TENSOR_MAP_L2_PROMOTION_L2_128B, CU_TENSOR_MAP_FLOAT_OOB_FILL_NONE);
    (void)r;
}

static void setup_params(Params& P, void* const* d_in, void* d_out) {
    void* fn = nullptr;
    cudaDriverEntryPointQueryResult qr;
    cudaGetDriverEntryPoint("cuTensorMapEncodeTiled", &fn, cudaEnableDefault, &qr);
    EncodeFn enc = (EncodeFn)fn;
    const bf16* q = (const bf16*)d_in[0];
    const bf16* k = (const bf16*)d_in[1];
    const bf16* v = (const bf16*)d_in[2];
    void *qkvc, *oc, *kvR, *zT;
    cudaGetSymbolAddress(&qkvc, g_qkvc);
    cudaGetSymbolAddress(&oc, g_oc);
    cudaGetSymbolAddress(&kvR, g_kvR);
    cudaGetSymbolAddress(&zT, g_zT);
    const CUtensorMapDataType BF = CU_TENSOR_MAP_DATA_TYPE_BFLOAT16, U64 = CU_TENSOR_MAP_DATA_TYPE_UINT64;
    const CUtensorMapSwizzle SW = CU_TENSOR_MAP_SWIZZLE_128B, NS = CU_TENSOR_MAP_SWIZZLE_NONE;
    make_map3(enc, &P.mW, BF, d_in[7], 64, 576, 27, 3456, 128, 64, MCAST ? 32 : 64, 3, SW);
    make_map(enc, &P.mX152, BF, 2, q, 576, SEQ, 64, TROWS, SW);
    make_map(enc, &P.mQ, U64, 8, qkvc, 2 * SEQ, 216, 256, 9, NS);
    make_map3(enc, &P.mKV, U64, qkvc, 128, 216, 32, SEQ * 16, 1024, 128, 9, 2, NS);
    make_map(enc, &P.mOst, U64, 8, oc, 2 * SEQ, 72, 128, 9, NS);
    make_map3(enc, &P.mOld, U64, oc, 2 * SEQ, 2, 72, 1280, SEQ * 16, 160, 2, 8, NS);
    make_map(enc, &P.mWo, BF, 2, d_in[8], 576, 576, 64, 64, SW);
    make_map(enc, &P.mK160, BF, 2, k, 576, SEQ, 64, 160, SW);
    make_map(enc, &P.mV152, BF, 2, v, 576, SEQ, 64, TROWS, SW);
    make_map(enc, &P.mKvR, BF, 2, kvR, KVR_PITCH, 576, TROWS, 64, NS);
    make_map(enc, &P.mZ, BF, 2, zT, SEQ, 576, TROWS, 64, NS);
    make_map(enc, &P.mOut, BF, 2, d_out, 576, SEQ, 64, TROWS, SW);
    P.x = q;
    P.shift_k = (const bf16*)d_in[3];
    P.ssm_k = (const bf16*)d_in[4];
    P.ssm_D = (const bf16*)d_in[5];
    P.gate_w = (const bf16*)d_in[9];
    P.wqkv = (const bf16*)d_in[7];
    P.wo = (const bf16*)d_in[8];
    P.mode = 0;
    cudaFuncSetAttribute(gated_mix_kernel, cudaFuncAttributeMaxDynamicSharedMemorySize, SMEM_BYTES);
}

static void launch(const Params& P) {
    cudaLaunchConfig_t cfg = {};
    cfg.gridDim = dim3(NCTA);
    cfg.blockDim = dim3(NTHREADS);
    cfg.dynamicSmemBytes = SMEM_BYTES;
    cfg.stream = cudaStreamPerThread;
    cudaLaunchAttribute at[1];
    at[0].id = cudaLaunchAttributeClusterDimension;
    at[0].val.clusterDim.x = MCAST ? 2 : 1;
    at[0].val.clusterDim.y = 1;
    at[0].val.clusterDim.z = 1;
    cfg.attrs = at;
    cfg.numAttrs = MCAST ? 1 : 0;
    cudaLaunchKernelEx(&cfg, gated_mix_kernel, P);
}

}

#define GM_MODE 1

extern "C" void kernel_launch(void* const* d_in, const int* in_sizes, int n_in, void* d_out, int out_size) {
    using namespace gm;
    (void)in_sizes; (void)n_in; (void)out_size;
    Params P;
    setup_params(P, d_in, d_out);
    P.mode = M_P1 | M_PRE | M_CONV | M_P2 | M_P3 | M_FUSED;
    launch(P);
}
```
